```python
import torch

def _softmax(x, axis=-1):
    return torch.softmax(x, dim=axis)
def _gelu(x):
    return torch.nn.functional.gelu(x, approximate="tanh")
def _silu(x):
    return torch.nn.functional.silu(x)
def _sigmoid(x):
    return torch.sigmoid(x)
def _layernorm(x, axis=-1, eps=1e-5):
    m = x.mean(dim=axis, keepdim=True)
    v = x.var(dim=axis, keepdim=True, unbiased=False)
    return (x - m) / torch.sqrt(v + eps)
def _scatter_add(tgt, idx, src, axis=0):
    return tgt.clone().index_add_(axis, idx, src)
def _segment_sum(src, seg, n):
    out = torch.zeros((n,) + src.shape[1:], dtype=src.dtype)
    return out.index_add_(0, seg, src)
def _pad(x, pw):
    flat = tuple(v for pair in reversed(pw) for v in pair)
    return torch.nn.functional.pad(x, flat)

kernel_name = 'gated_mix__sliding_local_dilated__spectral_fnet__prompt'

def setup_inputs():

    _w = (lambda a: (lambda t: t.to(torch.bfloat16) if t.is_floating_point() else t)(torch.as_tensor(a)))
    def _A_setup():
        B, S, D = 1, 2048, 1024
        return {
            "x": _w((lambda *s: torch.randn(*s, dtype=torch.bfloat16) * 0.05)(B, S, D)),
            "wqkv": _w((lambda *s: torch.randn(*s, dtype=torch.bfloat16) * 1.6)(D, 3 * D)),
            "wo": _w((lambda *s: torch.randn(*s, dtype=torch.bfloat16) * 0.2)(D, D)),
        }
    _A_in = _A_setup()

    def _B_setup():
        B, S, D = 1, 2048, 1024
        ns = torch.arange(S)[:, None] * torch.arange(S)[None, :]
        nd = torch.arange(D)[:, None] * torch.arange(D)[None, :]
        Ws_re = torch.cos(-2.0 * torch.pi * ns / S).to(float)
        Ws_im = torch.sin(-2.0 * torch.pi * ns / S).to(float)
        Wd_re = torch.cos(-2.0 * torch.pi * nd / D).to(float)
        Wd_im = torch.sin(-2.0 * torch.pi * nd / D).to(float)
        return {
            "x": _w((lambda *s: torch.randn(*s, dtype=torch.bfloat16) * 0.05)(B, S, D)),
            "dft_seq_re": _w(Ws_re),
            "dft_seq_im": _w(Ws_im),
            "dft_hid_re": _w(Wd_re),
            "dft_hid_im": _w(Wd_im),
        }
    _B_in = _B_setup()

    return {
        "A_x": _A_in["x"],
        "A_wqkv": _A_in["wqkv"],
        "A_wo": _A_in["wo"],
        "B_x": _B_in["x"],
        "B_dft_seq_re": _B_in["dft_seq_re"],
        "B_dft_seq_im": _B_in["dft_seq_im"],
        "B_dft_hid_re": _B_in["dft_hid_re"],
        "B_dft_hid_im": _B_in["dft_hid_im"],
        "gate_w": _w((lambda *s: torch.randn(*s, dtype=torch.bfloat16) * 0.05)(1024) * 16.0),
    }

def reference(A_x, A_wqkv, A_wo, B_x, B_dft_seq_re, B_dft_seq_im, B_dft_hid_re, B_dft_hid_im, gate_w):
    def _A_ref(x, wqkv, wo):
        B, S, D = x.shape
        H = 32; Dh = D // H
        W, dil = 8, 2
        qkv = (lambda x, *d: x.permute(*d))((x @ wqkv).reshape(B, S, 3, H, Dh), 2, 0, 3, 1, 4)
        q, k, v = qkv[0], qkv[1], qkv[2]
        scale = Dh ** -0.5
        pos = torch.arange(S)
        off = torch.arange(W) * dil
        idx = pos[:, None] - off[None, :]
        mask = idx >= 0
        idx_c = torch.where(mask, idx, 0).reshape(-1)
        kg = k[:, :, idx_c, :].reshape(B, H, S, W, Dh)
        vg = v[:, :, idx_c, :].reshape(B, H, S, W, Dh)
        logits = torch.einsum("bhsd,bhswd->bhsw", q, kg) * scale
        logits = torch.where(mask[None, None, :, :], logits, -1e9)
        attn = _softmax(logits, axis=-1)
        o = torch.einsum("bhsw,bhswd->bhsd", attn, vg)
        return (lambda x, *d: x.permute(*d))(o, 0, 2, 1, 3).reshape(B, S, D) @ wo

    def _B_ref(x, dft_seq_re, dft_seq_im, dft_hid_re, dft_hid_im):
        a = torch.einsum("bsd,ed->bse", x, dft_hid_re)
        b = torch.einsum("bsd,ed->bse", x, dft_hid_im)
        y = torch.einsum("ts,bse->bte", dft_seq_re, a) - torch.einsum("ts,bse->bte", dft_seq_im, b)
        return y

    x = A_x
    g = _sigmoid((x * gate_w).sum(-1, keepdims=True))
    a = _A_ref(x, A_wqkv, A_wo)
    b = _B_ref(x, B_dft_seq_re, B_dft_seq_im, B_dft_hid_re, B_dft_hid_im)
    return g * a + (1 - g) * b
```

```cpp
#include <cuda_runtime.h>
#include <cuda_bf16.h>
#include <cuda.h>
#include <stdint.h>
#include <stdio.h>

template <int TB>
__device__ __forceinline__ void wgmma_n256(float (&d)[128], uint64_t da, uint64_t db, int scale_d) {
  asm volatile(
    "{\n.reg .pred p;\nsetp.ne.b32 p, %130, 0;\n"
    "wgmma.mma_async.sync.aligned.m64n256k16.f32.bf16.bf16 "
    "{%0, %1, %2, %3, %4, %5, %6, %7, %8, %9, %10, %11, %12, %13, %14, %15, "
    "%16, %17, %18, %19, %20, %21, %22, %23, %24, %25, %26, %27, %28, %29, %30, %31, "
    "%32, %33, %34, %35, %36, %37, %38, %39, %40, %41, %42, %43, %44, %45, %46, %47, "
    "%48, %49, %50, %51, %52, %53, %54, %55, %56, %57, %58, %59, %60, %61, %62, %63, "
    "%64, %65, %66, %67, %68, %69, %70, %71, %72, %73, %74, %75, %76, %77, %78, %79, "
    "%80, %81, %82, %83, %84, %85, %86, %87, %88, %89, %90, %91, %92, %93, %94, %95, "
    "%96, %97, %98, %99, %100, %101, %102, %103, %104, %105, %106, %107, %108, %109, %110, %111, "
    "%112, %113, %114, %115, %116, %117, %118, %119, %120, %121, %122, %123, %124, %125, %126, %127}, "
    "%128, %129, p, 1, 1, 0, %131;\n}\n"
    : "+f"(d[0]), "+f"(d[1]), "+f"(d[2]), "+f"(d[3]), "+f"(d[4]), "+f"(d[5]), "+f"(d[6]), "+f"(d[7]),
      "+f"(d[8]), "+f"(d[9]), "+f"(d[10]), "+f"(d[11]), "+f"(d[12]), "+f"(d[13]), "+f"(d[14]), "+f"(d[15]),
      "+f"(d[16]), "+f"(d[17]), "+f"(d[18]), "+f"(d[19]), "+f"(d[20]), "+f"(d[21]), "+f"(d[22]), "+f"(d[23]),
      "+f"(d[24]), "+f"(d[25]), "+f"(d[26]), "+f"(d[27]), "+f"(d[28]), "+f"(d[29]), "+f"(d[30]), "+f"(d[31]),
      "+f"(d[32]), "+f"(d[33]), "+f"(d[34]), "+f"(d[35]), "+f"(d[36]), "+f"(d[37]), "+f"(d[38]), "+f"(d[39]),
      "+f"(d[40]), "+f"(d[41]), "+f"(d[42]), "+f"(d[43]), "+f"(d[44]), "+f"(d[45]), "+f"(d[46]), "+f"(d[47]),
      "+f"(d[48]), "+f"(d[49]), "+f"(d[50]), "+f"(d[51]), "+f"(d[52]), "+f"(d[53]), "+f"(d[54]), "+f"(d[55]),
      "+f"(d[56]), "+f"(d[57]), "+f"(d[58]), "+f"(d[59]), "+f"(d[60]), "+f"(d[61]), "+f"(d[62]), "+f"(d[63]),
      "+f"(d[64]), "+f"(d[65]), "+f"(d[66]), "+f"(d[67]), "+f"(d[68]), "+f"(d[69]), "+f"(d[70]), "+f"(d[71]),
      "+f"(d[72]), "+f"(d[73]), "+f"(d[74]), "+f"(d[75]), "+f"(d[76]), "+f"(d[77]), "+f"(d[78]), "+f"(d[79]),
      "+f"(d[80]), "+f"(d[81]), "+f"(d[82]), "+f"(d[83]), "+f"(d[84]), "+f"(d[85]), "+f"(d[86]), "+f"(d[87]),
      "+f"(d[88]), "+f"(d[89]), "+f"(d[90]), "+f"(d[91]), "+f"(d[92]), "+f"(d[93]), "+f"(d[94]), "+f"(d[95]),
      "+f"(d[96]), "+f"(d[97]), "+f"(d[98]), "+f"(d[99]), "+f"(d[100]), "+f"(d[101]), "+f"(d[102]), "+f"(d[103]),
      "+f"(d[104]), "+f"(d[105]), "+f"(d[106]), "+f"(d[107]), "+f"(d[108]), "+f"(d[109]), "+f"(d[110]), "+f"(d[111]),
      "+f"(d[112]), "+f"(d[113]), "+f"(d[114]), "+f"(d[115]), "+f"(d[116]), "+f"(d[117]), "+f"(d[118]), "+f"(d[119]),
      "+f"(d[120]), "+f"(d[121]), "+f"(d[122]), "+f"(d[123]), "+f"(d[124]), "+f"(d[125]), "+f"(d[126]), "+f"(d[127])
    : "l"(da), "l"(db), "r"(scale_d), "n"(TB));
}

template <int TA, int TB>
__device__ __forceinline__ void wgmma_n128t(float (&d)[64], uint64_t da, uint64_t db, int scale_d) {
  asm volatile(
    "{\n.reg .pred p;\nsetp.ne.b32 p, %66, 0;\n"
    "wgmma.mma_async.sync.aligned.m64n128k16.f32.bf16.bf16 "
    "{%0, %1, %2, %3, %4, %5, %6, %7, %8, %9, %10, %11, %12, %13, %14, %15, "
    "%16, %17, %18, %19, %20, %21, %22, %23, %24, %25, %26, %27, %28, %29, %30, %31, "
    "%32, %33, %34, %35, %36, %37, %38, %39, %40, %41, %42, %43, %44, %45, %46, %47, "
    "%48, %49, %50, %51, %52, %53, %54, %55, %56, %57, %58, %59, %60, %61, %62, %63}, "
    "%64, %65, p, 1, 1, %67, %68;\n}\n"
    : "+f"(d[0]), "+f"(d[1]), "+f"(d[2]), "+f"(d[3]), "+f"(d[4]), "+f"(d[5]), "+f"(d[6]), "+f"(d[7]),
      "+f"(d[8]), "+f"(d[9]), "+f"(d[10]), "+f"(d[11]), "+f"(d[12]), "+f"(d[13]), "+f"(d[14]), "+f"(d[15]),
      "+f"(d[16]), "+f"(d[17]), "+f"(d[18]), "+f"(d[19]), "+f"(d[20]), "+f"(d[21]), "+f"(d[22]), "+f"(d[23]),
      "+f"(d[24]), "+f"(d[25]), "+f"(d[26]), "+f"(d[27]), "+f"(d[28]), "+f"(d[29]), "+f"(d[30]), "+f"(d[31]),
      "+f"(d[32]), "+f"(d[33]), "+f"(d[34]), "+f"(d[35]), "+f"(d[36]), "+f"(d[37]), "+f"(d[38]), "+f"(d[39]),
      "+f"(d[40]), "+f"(d[41]), "+f"(d[42]), "+f"(d[43]), "+f"(d[44]), "+f"(d[45]), "+f"(d[46]), "+f"(d[47]),
      "+f"(d[48]), "+f"(d[49]), "+f"(d[50]), "+f"(d[51]), "+f"(d[52]), "+f"(d[53]), "+f"(d[54]), "+f"(d[55]),
      "+f"(d[56]), "+f"(d[57]), "+f"(d[58]), "+f"(d[59]), "+f"(d[60]), "+f"(d[61]), "+f"(d[62]), "+f"(d[63])
    : "l"(da), "l"(db), "r"(scale_d), "n"(TA), "n"(TB));
}

template <int OFF, int TB>
__device__ __forceinline__ void wgmma_n128_half(float (&d)[128], uint64_t da, uint64_t db) {
  asm volatile(
    "wgmma.mma_async.sync.aligned.m64n128k16.f32.bf16.bf16 "
    "{%0, %1, %2, %3, %4, %5, %6, %7, %8, %9, %10, %11, %12, %13, %14, %15, "
    "%16, %17, %18, %19, %20, %21, %22, %23, %24, %25, %26, %27, %28, %29, %30, %31, "
    "%32, %33, %34, %35, %36, %37, %38, %39, %40, %41, %42, %43, %44, %45, %46, %47, "
    "%48, %49, %50, %51, %52, %53, %54, %55, %56, %57, %58, %59, %60, %61, %62, %63}, "
    "%64, %65, 1, 1, 1, 0, %66;\n"
    : "+f"(d[OFF + 0]), "+f"(d[OFF + 1]), "+f"(d[OFF + 2]), "+f"(d[OFF + 3]), "+f"(d[OFF + 4]), "+f"(d[OFF + 5]),
      "+f"(d[OFF + 6]), "+f"(d[OFF + 7]), "+f"(d[OFF + 8]), "+f"(d[OFF + 9]), "+f"(d[OFF + 10]), "+f"(d[OFF + 11]),
      "+f"(d[OFF + 12]), "+f"(d[OFF + 13]), "+f"(d[OFF + 14]), "+f"(d[OFF + 15]), "+f"(d[OFF + 16]), "+f"(d[OFF + 17]),
      "+f"(d[OFF + 18]), "+f"(d[OFF + 19]), "+f"(d[OFF + 20]), "+f"(d[OFF + 21]), "+f"(d[OFF + 22]), "+f"(d[OFF + 23]),
      "+f"(d[OFF + 24]), "+f"(d[OFF + 25]), "+f"(d[OFF + 26]), "+f"(d[OFF + 27]), "+f"(d[OFF + 28]), "+f"(d[OFF + 29]),
      "+f"(d[OFF + 30]), "+f"(d[OFF + 31]), "+f"(d[OFF + 32]), "+f"(d[OFF + 33]), "+f"(d[OFF + 34]), "+f"(d[OFF + 35]),
      "+f"(d[OFF + 36]), "+f"(d[OFF + 37]), "+f"(d[OFF + 38]), "+f"(d[OFF + 39]), "+f"(d[OFF + 40]), "+f"(d[OFF + 41]),
      "+f"(d[OFF + 42]), "+f"(d[OFF + 43]), "+f"(d[OFF + 44]), "+f"(d[OFF + 45]), "+f"(d[OFF + 46]), "+f"(d[OFF + 47]),
      "+f"(d[OFF + 48]), "+f"(d[OFF + 49]), "+f"(d[OFF + 50]), "+f"(d[OFF + 51]), "+f"(d[OFF + 52]), "+f"(d[OFF + 53]),
      "+f"(d[OFF + 54]), "+f"(d[OFF + 55]), "+f"(d[OFF + 56]), "+f"(d[OFF + 57]), "+f"(d[OFF + 58]), "+f"(d[OFF + 59]),
      "+f"(d[OFF + 60]), "+f"(d[OFF + 61]), "+f"(d[OFF + 62]), "+f"(d[OFF + 63])
    : "l"(da), "l"(db), "n"(TB));
}

__device__ __forceinline__ void wgmma_n256_rs(float (&d)[128], uint32_t a0, uint32_t a1, uint32_t a2, uint32_t a3, uint64_t db, int scale_d) {
  asm volatile(
    "{\n.reg .pred p;\nsetp.ne.b32 p, %133, 0;\n"
    "wgmma.mma_async.sync.aligned.m64n256k16.f32.bf16.bf16 "
    "{%0, %1, %2, %3, %4, %5, %6, %7, %8, %9, %10, %11, %12, %13, %14, %15, "
    "%16, %17, %18, %19, %20, %21, %22, %23, %24, %25, %26, %27, %28, %29, %30, %31, "
    "%32, %33, %34, %35, %36, %37, %38, %39, %40, %41, %42, %43, %44, %45, %46, %47, "
    "%48, %49, %50, %51, %52, %53, %54, %55, %56, %57, %58, %59, %60, %61, %62, %63, "
    "%64, %65, %66, %67, %68, %69, %70, %71, %72, %73, %74, %75, %76, %77, %78, %79, "
    "%80, %81, %82, %83, %84, %85, %86, %87, %88, %89, %90, %91, %92, %93, %94, %95, "
    "%96, %97, %98, %99, %100, %101, %102, %103, %104, %105, %106, %107, %108, %109, %110, %111, "
    "%112, %113, %114, %115, %116, %117, %118, %119, %120, %121, %122, %123, %124, %125, %126, %127}, "
    "{%128, %129, %130, %131}, %132, p, 1, 1, 0;\n}\n"
    : "+f"(d[0]), "+f"(d[1]), "+f"(d[2]), "+f"(d[3]), "+f"(d[4]), "+f"(d[5]), "+f"(d[6]), "+f"(d[7]),
      "+f"(d[8]), "+f"(d[9]), "+f"(d[10]), "+f"(d[11]), "+f"(d[12]), "+f"(d[13]), "+f"(d[14]), "+f"(d[15]),
      "+f"(d[16]), "+f"(d[17]), "+f"(d[18]), "+f"(d[19]), "+f"(d[20]), "+f"(d[21]), "+f"(d[22]), "+f"(d[23]),
      "+f"(d[24]), "+f"(d[25]), "+f"(d[26]), "+f"(d[27]), "+f"(d[28]), "+f"(d[29]), "+f"(d[30]), "+f"(d[31]),
      "+f"(d[32]), "+f"(d[33]), "+f"(d[34]), "+f"(d[35]), "+f"(d[36]), "+f"(d[37]), "+f"(d[38]), "+f"(d[39]),
      "+f"(d[40]), "+f"(d[41]), "+f"(d[42]), "+f"(d[43]), "+f"(d[44]), "+f"(d[45]), "+f"(d[46]), "+f"(d[47]),
      "+f"(d[48]), "+f"(d[49]), "+f"(d[50]), "+f"(d[51]), "+f"(d[52]), "+f"(d[53]), "+f"(d[54]), "+f"(d[55]),
      "+f"(d[56]), "+f"(d[57]), "+f"(d[58]), "+f"(d[59]), "+f"(d[60]), "+f"(d[61]), "+f"(d[62]), "+f"(d[63]),
      "+f"(d[64]), "+f"(d[65]), "+f"(d[66]), "+f"(d[67]), "+f"(d[68]), "+f"(d[69]), "+f"(d[70]), "+f"(d[71]),
      "+f"(d[72]), "+f"(d[73]), "+f"(d[74]), "+f"(d[75]), "+f"(d[76]), "+f"(d[77]), "+f"(d[78]), "+f"(d[79]),
      "+f"(d[80]), "+f"(d[81]), "+f"(d[82]), "+f"(d[83]), "+f"(d[84]), "+f"(d[85]), "+f"(d[86]), "+f"(d[87]),
      "+f"(d[88]), "+f"(d[89]), "+f"(d[90]), "+f"(d[91]), "+f"(d[92]), "+f"(d[93]), "+f"(d[94]), "+f"(d[95]),
      "+f"(d[96]), "+f"(d[97]), "+f"(d[98]), "+f"(d[99]), "+f"(d[100]), "+f"(d[101]), "+f"(d[102]), "+f"(d[103]),
      "+f"(d[104]), "+f"(d[105]), "+f"(d[106]), "+f"(d[107]), "+f"(d[108]), "+f"(d[109]), "+f"(d[110]), "+f"(d[111]),
      "+f"(d[112]), "+f"(d[113]), "+f"(d[114]), "+f"(d[115]), "+f"(d[116]), "+f"(d[117]), "+f"(d[118]), "+f"(d[119]),
      "+f"(d[120]), "+f"(d[121]), "+f"(d[122]), "+f"(d[123]), "+f"(d[124]), "+f"(d[125]), "+f"(d[126]), "+f"(d[127])
    : "r"(a0), "r"(a1), "r"(a2), "r"(a3), "l"(db), "r"(scale_d));
}

__device__ __forceinline__ uint32_t smem_u32(const void* p) { return (uint32_t)__cvta_generic_to_shared(p); }
__device__ __forceinline__ void mbar_init(uint32_t bar, uint32_t cnt) {
  asm volatile("mbarrier.init.shared::cta.b64 [%0], %1;" ::"r"(bar), "r"(cnt) : "memory");
}
__device__ __forceinline__ void mbar_expect_tx(uint32_t bar, uint32_t bytes) {
  asm volatile("mbarrier.arrive.expect_tx.shared::cta.b64 _, [%0], %1;" ::"r"(bar), "r"(bytes) : "memory");
}
__device__ __forceinline__ void mbar_arrive(uint32_t bar) {
  asm volatile("mbarrier.arrive.shared::cta.b64 _, [%0];" ::"r"(bar) : "memory");
}
__device__ __forceinline__ void mbar_wait(uint32_t bar, uint32_t parity) {
  asm volatile(
      "{\n.reg .pred p;\n.reg .u32 c;\nmov.u32 c, 0;\n"
      "LAB_WAIT:\nmbarrier.try_wait.parity.shared::cta.b64 p, [%0], %1;\n@p bra DONE;\n"
      "add.u32 c, c, 1;\nsetp.lt.u32 p, c, 0x400000;\n@p bra LAB_WAIT;\ntrap;\nDONE:\n}\n" ::"r"(bar),
      "r"(parity)
      : "memory");
}
__device__ __forceinline__ void mbar_wait_cluster(uint32_t bar, uint32_t parity) {
  asm volatile(
      "{\n.reg .pred p;\n.reg .u32 c;\nmov.u32 c, 0;\n"
      "LAB_WAIT:\nmbarrier.try_wait.parity.acquire.cluster.shared::cta.b64 p, [%0], %1;\n@p bra DONE;\n"
      "add.u32 c, c, 1;\nsetp.lt.u32 p, c, 0x400000;\n@p bra LAB_WAIT;\ntrap;\nDONE:\n}\n" ::"r"(bar),
      "r"(parity)
      : "memory");
}
__device__ __forceinline__ uint32_t mapa(uint32_t addr, uint32_t cta) {
  uint32_t r;
  asm volatile("mapa.shared::cluster.u32 %0, %1, %2;" : "=r"(r) : "r"(addr), "r"(cta));
  return r;
}
__device__ __forceinline__ void tma_ld2(uint32_t dst, const CUtensorMap* tm, uint32_t bar, int c0, int c1) {
  asm volatile(
      "cp.async.bulk.tensor.2d.shared::cluster.global.mbarrier::complete_tx::bytes [%0], [%1, {%3, %4}], [%2];" ::"r"(dst),
      "l"(tm), "r"(bar), "r"(c0), "r"(c1)
      : "memory");
}
__device__ __forceinline__ void tma_ld3(uint32_t dst, const CUtensorMap* tm, uint32_t bar, int c0, int c1, int c2) {
  asm volatile(
      "cp.async.bulk.tensor.3d.shared::cluster.global.mbarrier::complete_tx::bytes [%0], [%1, {%3, %4, %5}], [%2];" ::"r"(dst),
      "l"(tm), "r"(bar), "r"(c0), "r"(c1), "r"(c2)
      : "memory");
}
__device__ __forceinline__ void tma_ld5(uint32_t dst, const CUtensorMap* tm, uint32_t bar, int c0, int c1, int c2, int c3,
                                        int c4) {
  asm volatile(
      "cp.async.bulk.tensor.5d.shared::cluster.global.mbarrier::complete_tx::bytes [%0], [%1, {%3, %4, %5, %6, %7}], [%2];" ::"r"(dst),
      "l"(tm), "r"(bar), "r"(c0), "r"(c1), "r"(c2), "r"(c3), "r"(c4)
      : "memory");
}
__device__ __forceinline__ void tma_ld2_mc(uint32_t dst, const CUtensorMap* tm, uint32_t bar, int c0, int c1) {
  asm volatile(
      "cp.async.bulk.tensor.2d.shared::cluster.global.mbarrier::complete_tx::bytes.multicast::cluster [%0], [%1, {%3, %4}], [%2], %5;" ::"r"(dst),
      "l"(tm), "r"(bar), "r"(c0), "r"(c1), "h"((uint16_t)3)
      : "memory");
}
__device__ __forceinline__ void tma_ld3_mc(uint32_t dst, const CUtensorMap* tm, uint32_t bar, int c0, int c1, int c2) {
  asm volatile(
      "cp.async.bulk.tensor.3d.shared::cluster.global.mbarrier::complete_tx::bytes.multicast::cluster [%0], [%1, {%3, %4, %5}], [%2], %6;" ::"r"(dst),
      "l"(tm), "r"(bar), "r"(c0), "r"(c1), "r"(c2), "h"((uint16_t)3)
      : "memory");
}
__device__ __forceinline__ void tma_ld5_mc(uint32_t dst, const CUtensorMap* tm, uint32_t bar, int c0, int c1, int c2, int c3,
                                           int c4) {
  asm volatile(
      "cp.async.bulk.tensor.5d.shared::cluster.global.mbarrier::complete_tx::bytes.multicast::cluster [%0], [%1, {%3, %4, %5, %6, %7}], [%2], %8;" ::"r"(dst),
      "l"(tm), "r"(bar), "r"(c0), "r"(c1), "r"(c2), "r"(c3), "r"(c4), "h"((uint16_t)3)
      : "memory");
}
__device__ __forceinline__ void mbar_arrive_cl(uint32_t cluster_addr) {
  asm volatile("mbarrier.arrive.shared::cluster.b64 _, [%0];" ::"r"(cluster_addr) : "memory");
}
__device__ __forceinline__ void tma_st2(const CUtensorMap* tm, uint32_t src, int c0, int c1) {
  asm volatile("cp.async.bulk.tensor.2d.global.shared::cta.bulk_group [%0, {%2, %3}], [%1];" ::"l"(tm), "r"(src), "r"(c0),
               "r"(c1)
               : "memory");
}
__device__ __forceinline__ void bulk_commit() { asm volatile("cp.async.bulk.commit_group;" ::: "memory"); }
__device__ __forceinline__ void bulk_wait_read0() { asm volatile("cp.async.bulk.wait_group.read 0;" ::: "memory"); }
__device__ __forceinline__ void bulk_wait0() { asm volatile("cp.async.bulk.wait_group 0;" ::: "memory"); }
__device__ __forceinline__ void fence_async_smem() { asm volatile("fence.proxy.async.shared::cta;" ::: "memory"); }
__device__ __forceinline__ void prefetch_tmap(const CUtensorMap* tm) {
  asm volatile("prefetch.tensormap [%0];" ::"l"(tm) : "memory");
}
__device__ __forceinline__ void wgmma_fence() { asm volatile("wgmma.fence.sync.aligned;" ::: "memory"); }
__device__ __forceinline__ void wgmma_commit() { asm volatile("wgmma.commit_group.sync.aligned;" ::: "memory"); }
template <int N>
__device__ __forceinline__ void wgmma_wait() {
  asm volatile("wgmma.wait_group.sync.aligned %0;" ::"n"(N) : "memory");
}
__device__ __forceinline__ uint32_t pack_bf16(float lo, float hi) {
  uint32_t r;
  asm("cvt.rn.bf16x2.f32 %0, %1, %2;" : "=r"(r) : "f"(hi), "f"(lo));
  return r;
}
__device__ __forceinline__ uint32_t pack_bf16v(float lo, float hi) {
  uint32_t r;
  asm volatile("cvt.rn.bf16x2.f32 %0, %1, %2;" : "=r"(r) : "f"(hi), "f"(lo));
  return r;
}
__device__ __forceinline__ uint32_t mul_bf16x2v(uint32_t a, uint32_t b) {
  uint32_t r;
  asm volatile("mul.rn.bf16x2 %0, %1, %2;" : "=r"(r) : "r"(a), "r"(b));
  return r;
}
__device__ __forceinline__ float bf_lo(uint32_t v) { return __uint_as_float(v << 16); }
__device__ __forceinline__ float bf_hi(uint32_t v) { return __uint_as_float(v & 0xFFFF0000u); }
__device__ __forceinline__ float round_bf16(float v) { return __bfloat162float(__float2bfloat16_rn(v)); }
__device__ __forceinline__ uint32_t movmatrix_t(uint32_t a) {
  uint32_t d;
  asm volatile("movmatrix.sync.aligned.m8n8.trans.b16 %0, %1;" : "=r"(d) : "r"(a));
  return d;
}
__device__ __forceinline__ void stmatrix_x4(uint32_t addr, uint32_t r0, uint32_t r1, uint32_t r2, uint32_t r3) {
  asm volatile("stmatrix.sync.aligned.m8n8.x4.shared.b16 [%0], {%1, %2, %3, %4};" ::"r"(addr), "r"(r0), "r"(r1), "r"(r2),
               "r"(r3)
               : "memory");
}
__device__ __forceinline__ void stmatrix_x4_t(uint32_t addr, uint32_t r0, uint32_t r1, uint32_t r2, uint32_t r3) {
  asm volatile("stmatrix.sync.aligned.m8n8.x4.trans.shared.b16 [%0], {%1, %2, %3, %4};" ::"r"(addr), "r"(r0), "r"(r1),
               "r"(r2), "r"(r3)
               : "memory");
}
__device__ __forceinline__ void stmatrix_x2_t(uint32_t addr, uint32_t r0, uint32_t r1) {
  asm volatile("stmatrix.sync.aligned.m8n8.x2.trans.shared.b16 [%0], {%1, %2};" ::"r"(addr), "r"(r0), "r"(r1) : "memory");
}
__device__ __forceinline__ uint2 ldcg64(const uint2* p) {
  uint2 v;
  asm volatile("ld.relaxed.gpu.global.v2.u32 {%0, %1}, [%2];" : "=r"(v.x), "=r"(v.y) : "l"(p) : "memory");
  return v;
}
__device__ __forceinline__ void mma_k16(float (&c)[4], uint32_t a0, uint32_t a1, uint32_t a2, uint32_t a3, uint32_t b0,
                                        uint32_t b1) {
  asm volatile(
      "mma.sync.aligned.m16n8k16.row.col.f32.bf16.bf16.f32 {%0, %1, %2, %3}, {%4, %5, %6, %7}, {%8, %9}, {%0, %1, %2, %3};"
      : "+f"(c[0]), "+f"(c[1]), "+f"(c[2]), "+f"(c[3])
      : "r"(a0), "r"(a1), "r"(a2), "r"(a3), "r"(b0), "r"(b1));
}
__device__ __forceinline__ void sts128(uint32_t addr, uint32_t a, uint32_t b, uint32_t c, uint32_t d) {
  asm volatile("st.shared.v4.b32 [%0], {%1, %2, %3, %4};" ::"r"(addr), "r"(a), "r"(b), "r"(c), "r"(d) : "memory");
}
__device__ __forceinline__ uint4 lds128(uint32_t addr) {
  uint4 v;
  asm volatile("ld.shared.v4.b32 {%0, %1, %2, %3}, [%4];" : "=r"(v.x), "=r"(v.y), "=r"(v.z), "=r"(v.w) : "r"(addr) : "memory");
  return v;
}
__device__ __forceinline__ float lds_f32(uint32_t addr) {
  float v;
  asm volatile("ld.shared.f32 %0, [%1];" : "=f"(v) : "r"(addr) : "memory");
  return v;
}
__device__ __forceinline__ void sts_f32(uint32_t addr, float v) {
  asm volatile("st.shared.f32 [%0], %1;" ::"r"(addr), "f"(v) : "memory");
}
__device__ __forceinline__ unsigned ld_acquire(const unsigned* p) {
  unsigned v;
  asm volatile("ld.acquire.gpu.global.u32 %0, [%1];" : "=r"(v) : "l"(p) : "memory");
  return v;
}
__device__ __forceinline__ unsigned ld_relaxed(const unsigned* p) {
  unsigned v;
  asm volatile("ld.relaxed.gpu.global.u32 %0, [%1];" : "=r"(v) : "l"(p) : "memory");
  return v;
}
__device__ __forceinline__ void st_release(unsigned* p, unsigned v) {
  asm volatile("st.release.gpu.global.u32 [%0], %1;" ::"l"(p), "r"(v) : "memory");
}
__device__ __forceinline__ void red_release_add(unsigned* p, unsigned v) {
  asm volatile("red.release.gpu.global.add.u32 [%0], %1;" ::"l"(p), "r"(v) : "memory");
}
__device__ __forceinline__ void poll_ge(const unsigned* p, unsigned target) {
  unsigned n = 0;
  while ((int)(ld_acquire(p) - target) < 0) {
    __nanosleep(100);
    if (++n > 2000000u) __trap();
  }
}
__device__ __forceinline__ uint4 ldcg128(const uint4* p) {
  uint4 v;
  asm volatile("ld.relaxed.gpu.global.v4.u32 {%0, %1, %2, %3}, [%4];"
               : "=r"(v.x), "=r"(v.y), "=r"(v.z), "=r"(v.w)
               : "l"(p)
               : "memory");
  return v;
}
__device__ __forceinline__ void bulk_copy_cl(uint32_t rdst, uint32_t src, uint32_t bytes, uint32_t rbar) {
  asm volatile("cp.async.bulk.shared::cluster.shared::cta.mbarrier::complete_tx::bytes [%0], [%1], %2, [%3];" ::"r"(rdst),
               "r"(src), "r"(bytes), "r"(rbar)
               : "memory");
}
__device__ __forceinline__ float ex2_fast(float x) {
  float y;
  asm("ex2.approx.ftz.f32 %0, %1;" : "=f"(y) : "f"(x));
  return y;
}
__device__ __forceinline__ float rcp_fast(float x) {
  float y;
  asm("rcp.approx.ftz.f32 %0, %1;" : "=f"(y) : "f"(x));
  return y;
}
template <int LO, int HI, int N>
__device__ __forceinline__ void fence_regs(float (&a)[N]) {
#pragma unroll
  for (int i = LO; i < HI; i++) asm volatile("" : "+f"(a[i])::"memory");
}
__device__ __forceinline__ void named_bar_arrive(int id, int n) { asm volatile("bar.arrive %0, %1;" ::"r"(id), "r"(n) : "memory"); }
__device__ __forceinline__ void named_bar_sync(int id, int n) { asm volatile("bar.sync %0, %1;" ::"r"(id), "r"(n) : "memory"); }

constexpr int SEQ = 2048, DM = 1024;
constexpr int ZW = 3072;

__device__ __align__(1024) __nv_bfloat16 g_Z[SEQ * ZW];
__device__ __align__(16) float g_gate[SEQ];
__device__ uint4 g_edge[256 * 12 * 32];
constexpr int SY_EPOCH = 0, SY_GCNT = 8, SY_O = 16, SY_PQ = SY_O + 16, SY_EDGE = SY_PQ + 64, SY_N = SY_EDGE + 256;
__device__ unsigned g_sync[SY_N * 8];

struct Params {
  CUtensorMap xa1, wq1, xa, wqkv, c0, c1, xb, zl, zs, zo, d0, d1, wo, out;
  const __nv_bfloat16* x;
  const __nv_bfloat16* gate_w;
};

constexpr int KB3 = 4;
constexpr int IT_B = 72 - KB3 / 2, IT_END = IT_B + (2 * KB3 + 2) / 3;

constexpr uint32_t ST1 = 57344, ST1_A = 24576;
constexpr uint32_t ST2 = 49152, ST2_A = 32768;
constexpr uint32_t SPARE = 196608;
constexpr uint32_t MISC = 229376;
constexpr uint32_t B_FULL = MISC, B_EMPTY = MISC + 32, B_STG = MISC + 64, B_FREE = MISC + 128, B_RECV = MISC + 160,
                   B_G = MISC + 176, B_DEP = MISC + 184, S_EPOCH = MISC + 216, B_F0 = MISC + 224, B_EDGE = MISC + 256,
                   B_X2 = MISC + 272, B_F1 = MISC + 288, S_G1 = MISC + 304, S_G2 = S_G1 + 1024;
constexpr uint32_t SMEM_BYTES = S_G2 + 512;
static_assert(SMEM_BYTES <= 232448, "smem");


__device__ __forceinline__ uint64_t desc_from(uint32_t lo) {
  uint64_t d;
  asm("mov.b64 %0, {%1, %2};" : "=l"(d) : "r"(lo), "r"(0x40000040u));
  return d;
}
constexpr uint32_t LBO_K = 1u << 16, LBO_MN = (8192u >> 4) << 16;
__device__ __forceinline__ uint64_t desc_k(uint32_t addr16, int k) { return desc_from(addr16 + LBO_K + k * 2); }
__device__ __forceinline__ uint64_t desc_mn(uint32_t addr16, int k) { return desc_from(addr16 + LBO_MN + k * 128); }
template <int TB>
__device__ __forceinline__ void mma256(float (&acc)[128], uint32_t a16, uint32_t b16, int k, int accumulate) {
  wgmma_n256<TB>(acc, desc_k(a16, k), TB ? desc_mn(b16, k) : desc_k(b16, k), accumulate);
}
__device__ __forceinline__ int dcol(int jb, int i) {
  const int half = i >= 6, r = half ? i - 6 : i, t = r >> 1;
  return ((t + (t >= jb)) * 4 + half * 2 + (r & 1)) * 64;
}

__global__ void __cluster_dims__(2, 1, 1) __launch_bounds__(384, 1) fused_kernel(const __grid_constant__ Params p) {
  extern __shared__ __align__(1024) uint8_t smem_raw[];
  const uint32_t sb = smem_u32(smem_raw);
  const int tid = threadIdx.x, warp = __shfl_sync(0xffffffffu, tid >> 5, 0), lane = tid & 31;
  uint32_t rank;
  asm volatile("mov.u32 %0, %%cluster_ctarank;" : "=r"(rank));
  const int cl = blockIdx.x >> 1;
  const int pb = cl >> 3, hp = (cl & 7) * 2 + (int)rank;
  const int rb = cl >> 2, jb = cl & 3;

  if (tid == 0) {
    if (sb & 1023) __trap();
    mbar_init(sb + B_FULL, 1);
    for (int s = 0; s < 4; s++) mbar_init(sb + B_F0 + 8 * s, 1);
    mbar_expect_tx(sb + B_F0, 8192);
    tma_ld5(sb + ST1_A, &p.xa1, sb + B_F0, 0, 0, pb * 4, 0, 0);
    mbar_init(sb + B_F1, 1);
    mbar_expect_tx(sb + B_F1, 8192);
    tma_ld3(sb, &p.wq1, sb + B_F1, hp * 64, 0, 0);
    tma_ld3(sb + 8192, &p.wq1, sb + B_F1, hp * 64, 0, 1);
    mbar_expect_tx(sb + B_FULL, ST1_A - 8192);
    tma_ld3(sb + 4096, &p.wq1, sb + B_FULL, hp * 64, 32, 0);
    tma_ld3(sb + 12288, &p.wq1, sb + B_FULL, hp * 64, 32, 1);
#pragma unroll
    for (int j = 1; j < 4; j++) {
      mbar_expect_tx(sb + B_F0 + 8 * j, 8192);
      tma_ld5(sb + ST1_A + (j & 1) * 16384 + (j >> 1) * 8192, &p.xa1, sb + B_F0 + 8 * j, 0, 0, pb * 4, j >> 1, j & 1);
      if (j == 1) {
        tma_ld3(sb + 16384, &p.wq1, sb + B_FULL, hp * 64, 0, 2);
        tma_ld3(sb + 20480, &p.wq1, sb + B_FULL, hp * 64, 32, 2);
      }
    }
    asm volatile("fence.mbarrier_init.release.cluster;" ::: "memory");
  } else if (tid == 32) {
    prefetch_tmap(&p.wq1);
    prefetch_tmap(&p.wqkv);
    prefetch_tmap(&p.xa);
    for (int s = 0; s < 4; s++) {
      if (s) mbar_init(sb + B_FULL + 8 * s, 1);
      mbar_init(sb + B_EMPTY + 8 * s, 4);
      mbar_init(sb + B_DEP + 8 * s, 1);
      mbar_init(sb + B_FREE + 8 * s, 1);
    }
    for (int s = 0; s < 8; s++) mbar_init(sb + B_STG + 8 * s, 4);
    mbar_init(sb + B_RECV, 1);
    mbar_init(sb + B_RECV + 8, 1);
    mbar_init(sb + B_G, 1);
    mbar_init(sb + B_X2, 4);
    mbar_init(sb + B_X2 + 8, 4);
    mbar_init(sb + B_EDGE, 4);
    mbar_init(sb + B_EDGE + 8, 4);
    asm volatile("fence.mbarrier_init.release.cluster;" ::: "memory");
    mbar_expect_tx(sb + B_RECV, 16384);
    mbar_expect_tx(sb + B_RECV + 8, 16384);
  }
  __syncthreads();
  asm volatile("barrier.cluster.arrive.relaxed.aligned;" ::: "memory");

  if (warp < 4) {
    asm volatile("setmaxnreg.dec.sync.aligned.u32 %0;" ::"n"(56));
    if (warp == 0) {
      if (lane == 0) {
        const uint32_t full = sb + B_FULL + 8, base = sb + ST1;
        mbar_expect_tx(full, ST1);
        tma_ld3(base, &p.wqkv, full, hp * 64, 64, 0);
        tma_ld5(base + ST1_A, &p.xa, full, 64, 0, pb * 4, 0, 0);
        tma_ld5(base + ST1_A + 16384, &p.xa, full, 64, 0, pb * 4, 0, 1);
      }
      __syncwarp();
      asm volatile("barrier.cluster.wait.aligned;" ::: "memory");
      if (lane == 0) {
        const CUtensorMap* tc = rank ? &p.c1 : &p.c0;
        const CUtensorMap* td = rank ? &p.d1 : &p.d0;
        const int keep = jb * 2 + (int)rank, send = jb * 2 + 1 - (int)rank;
#pragma unroll 1
        for (int it = 2; it < IT_END; it++) {
          const uint32_t s = it & 3, full = sb + B_FULL + 8 * s;
          if (it == 2) mbar_wait(sb + B_F0 + 24, 0);
          mbar_wait(sb + B_EMPTY + 8 * s, ((it >> 2) & 1) ^ 1);
          if (it < 16) {
            const uint32_t base = sb + s * ST1;
            mbar_expect_tx(full, ST1);
            tma_ld5_mc(base + ST1_A + rank * 16384, &p.xa, full, it * 64, 0, pb * 4, 0, (int)rank);
            tma_ld3(base, &p.wqkv, full, hp * 64, it * 64, 0);
          } else {
            const uint32_t base = sb + s * ST2;
            if (it < 48) {
              mbar_expect_tx(full, ST2);
              tma_ld3_mc(base + rank * 16384, &p.xb, full, 0, (it - 16) * 64, jb * 4 + (int)rank * 2);
              tma_ld2(base + ST2_A, tc, full, (it - 16) * 64, rb * 128);
            } else if (it >= 52 && it < 56) {
              const int kc = jb * 256 + (it - 52) * 64;
              mbar_expect_tx(full, 32768);
              tma_ld2(base, td, full, kc, keep * 128);
              tma_ld2(base + 16384, td, full, kc, send * 128);
            } else if (it < 60) {
              const int kc = (int)rank * 512 + (it < 52 ? it - 48 : it - 52) * 64;
              mbar_expect_tx(full, ST2);
              tma_ld3(base, &p.wo, full, 0, kc, keep * 2);
              tma_ld3(base + 16384, &p.wo, full, 0, kc, send * 2);
              if (it == 48) mbar_wait(sb + B_DEP, 0);
              tma_ld2(base + ST2_A, &p.zl, full, kc, rb * 128);
            } else if (it < IT_B) {
              const int kc = dcol(jb, it - 60);
              mbar_expect_tx(full, ST2);
              tma_ld2(base, td, full, kc, keep * 128);
              tma_ld2(base + 16384, td, full, kc, send * 128);
              if (it == 60) mbar_wait(sb + B_DEP + 8, 0);
              if (it == 66) mbar_wait(sb + B_DEP + 16, 0);
              tma_ld2(base + ST2_A, &p.zl, full, 1024 + (int)rank * 1024 + kc, rb * 128);
            } else {
              const int p0 = (it - IT_B) * 3, np = min(3, 2 * KB3 - p0);
              mbar_expect_tx(full, np * 16384);
              if (p0 == 0) mbar_wait(sb + B_DEP + 24, 0);
#pragma unroll 1
              for (int j = 0; j < np; j++) {
                const int pc = p0 + j, i = pc >> 1;
                const int ty = i >= KB3 / 2;
                const int kc = dcol(jb, 12 - KB3 / 2 + (ty ? i - KB3 / 2 : i));
                if (pc & 1) tma_ld2(base + j * 16384, ty ? &p.d1 : &p.d0, full, kc, keep * 128);
                else tma_ld2_mc(base + j * 16384 + rank * 8192, &p.zs, full, 1024 + ty * 1024 + kc, rb * 128 + (int)rank * 64);
              }
            }
          }
        }
      }
    } else {
      asm volatile("barrier.cluster.wait.aligned;" ::: "memory");
      unsigned epoch = 0;
      if (warp == 1) {
        if (lane == 0) {
          prefetch_tmap(rank ? &p.c1 : &p.c0);
          prefetch_tmap(&p.xb);
          prefetch_tmap(&p.zl);
          prefetch_tmap(&p.zs);
          prefetch_tmap(&p.zo);
          prefetch_tmap(&p.d0);
          prefetch_tmap(&p.d1);
          prefetch_tmap(&p.wo);
          prefetch_tmap(&p.out);
        }
        epoch = ld_relaxed(&g_sync[(SY_EPOCH + pb) * 8]);
      }
      mbar_wait(sb + B_F0 + 24, 0);
#pragma unroll 1
      for (int r = 2 * (warp - 1); r < 16; r += 6) {
        const int row = blockIdx.x * 16 + r;
        const uint4* xr = reinterpret_cast<const uint4*>(p.x + (size_t)row * DM) + lane;
        uint4 a[8];
#pragma unroll
        for (int i = 0; i < 8; i++) a[i] = __ldg(xr + i * 32);
        float acc[2] = {0.f, 0.f};
#pragma unroll
        for (int i = 0; i < 4; i++) {
          const uint4 w = __ldg(reinterpret_cast<const uint4*>(p.gate_w) + i * 32 + lane);
          const uint32_t wv[4] = {w.x, w.y, w.z, w.w};
#pragma unroll
          for (int t = 0; t < 2; t++) {
            const uint32_t av[4] = {a[4 * t + i].x, a[4 * t + i].y, a[4 * t + i].z, a[4 * t + i].w};
#pragma unroll
            for (int j = 0; j < 4; j++) {
              const uint32_t pr = pack_bf16(bf_lo(av[j]) * bf_lo(wv[j]), bf_hi(av[j]) * bf_hi(wv[j]));
              acc[t] += bf_lo(pr) + bf_hi(pr);
            }
          }
        }
#pragma unroll
        for (int o = 16; o; o >>= 1) {
          acc[0] += __shfl_xor_sync(0xffffffffu, acc[0], o);
          acc[1] += __shfl_xor_sync(0xffffffffu, acc[1], o);
        }
        if (lane == 0) {
          g_gate[row] = round_bf16(1.f / (1.f + __expf(-round_bf16(acc[0]))));
          g_gate[row + 1] = round_bf16(1.f / (1.f + __expf(-round_bf16(acc[1]))));
        }
      }
      if (lane == 0) red_release_add(&g_sync[(SY_GCNT + pb) * 8], 1);
      if (warp == 1) {
        poll_ge(&g_sync[(SY_GCNT + pb) * 8], (epoch + 1) * 48);
        if ((blockIdx.x & 15) == 0 && lane == 0) g_sync[(SY_EPOCH + pb) * 8] = epoch + 1;
        const uint4* gg = reinterpret_cast<const uint4*>(g_gate + pb * 256) + lane * 2;
        const uint4 u = ldcg128(gg), v = ldcg128(gg + 1);
        sts128(sb + S_G1 + lane * 16, u.x, u.z, v.x, v.z);
        sts128(sb + S_G1 + 512 + lane * 16, u.y, u.w, v.y, v.w);
        if ((lane >> 4) == (rb & 1)) {
          const float sg = rank ? -1.f : 1.f;
          const uint32_t gv[8] = {u.x, u.y, u.z, u.w, v.x, v.y, v.z, v.w};
#pragma unroll
          for (int i = 0; i < 8; i++)
            sts_f32(sb + S_G2 + ((lane & 15) * 8 + i) * 4, sg * round_bf16(1.f - __uint_as_float(gv[i])));
        }
        if (lane == 0) asm volatile("st.shared.u32 [%0], %1;" ::"r"(sb + S_EPOCH), "r"(epoch) : "memory");
        __syncwarp();
        if (lane == 0) {
          mbar_arrive(sb + B_G);
          mbar_wait(sb + B_FREE + 8, 0);
          poll_ge(&g_sync[(SY_O + pb * 2 + rank) * 8], (epoch + 1) * 16);
          mbar_arrive(sb + B_DEP);
          mbar_wait(sb + B_FREE + 24, 0);
          poll_ge(&g_sync[(SY_PQ + rb * 4 + rank * 2) * 8], (epoch + 1) * 4);
          mbar_arrive(sb + B_DEP + 8);
          poll_ge(&g_sync[(SY_PQ + rb * 4 + rank * 2 + 1) * 8], (epoch + 1) * 4);
          mbar_arrive(sb + B_DEP + 16);
          poll_ge(&g_sync[(SY_PQ + rb * 4 + (rank ^ 1) * 2 + 1) * 8], (epoch + 1) * 4);
          mbar_arrive(sb + B_DEP + 24);
        }
        __syncwarp();
      } else {
        const int cw = warp - 2;
        mbar_wait(sb + B_G, 0);
        asm volatile("ld.shared.u32 %0, [%1];" : "=r"(epoch) : "r"(sb + S_EPOCH) : "memory");
        const uint32_t stg = sb + SPARE + cw * 16384;
        const int eid = (pb * 16 + hp) * 2 + cw;
        mbar_wait(sb + B_EDGE + 8 * cw, 0);
        if (lane == 0) st_release(&g_sync[(SY_EDGE + eid) * 8], epoch + 1);
        if (pb > 0) poll_ge(&g_sync[(SY_EDGE + eid - 32) * 8], epoch + 1);
        {
          const int g = lane >> 2, q = lane & 3;
          const uint4* ef = g_edge + eid * 12 * 32 + lane;
          const uint4* el = g_edge + (pb > 0 ? eid - 32 : eid) * 12 * 32 + lane;
          const float gate = lds_f32(sb + S_G1 + (cw * 128 + g) * 4);
          const bool valid_prev = pb > 0;
#pragma unroll 1
          for (int h = 0; h < 2; h++) {
            const uint4 qa = ldcg128(ef + 2 * h * 32), qb = ldcg128(ef + (2 * h + 1) * 32);
            uint4 f = ldcg128(ef + (4 + h) * 32), l = ldcg128(el + (6 + h) * 32);
            const uint2 vf0 = ldcg64(reinterpret_cast<const uint2*>(ef + (8 + 2 * h) * 32));
            const uint2 vf1 = ldcg64(reinterpret_cast<const uint2*>(ef + (9 + 2 * h) * 32));
            const uint2 vl0 = ldcg64(reinterpret_cast<const uint2*>(el + (8 + 2 * h) * 32) + 1);
            const uint2 vl1 = ldcg64(reinterpret_cast<const uint2*>(el + (9 + 2 * h) * 32) + 1);
            const uint4 qv = make_uint4(qa.x, qa.z, qb.x, qb.z);
            float lg[8];
#pragma unroll
            for (int w = 0; w < 8; w++) {
              const bool cur = g + w <= 7;
              const int src = (((g - w) & 7) << 2) | q;
              const uint32_t k0 = __shfl_sync(0xffffffffu, cur ? f.x : l.x, src), k1 = __shfl_sync(0xffffffffu, cur ? f.y : l.y, src);
              const uint32_t k2 = __shfl_sync(0xffffffffu, cur ? f.z : l.z, src), k3 = __shfl_sync(0xffffffffu, cur ? f.w : l.w, src);
              float d = bf_lo(qv.x) * bf_lo(k0) + bf_hi(qv.x) * bf_hi(k0) + bf_lo(qv.y) * bf_lo(k1) + bf_hi(qv.y) * bf_hi(k1) +
                        bf_lo(qv.z) * bf_lo(k2) + bf_hi(qv.z) * bf_hi(k2) + bf_lo(qv.w) * bf_lo(k3) + bf_hi(qv.w) * bf_hi(k3);
              d += __shfl_xor_sync(0xffffffffu, d, 1);
              d += __shfl_xor_sync(0xffffffffu, d, 2);
              lg[w] = (g >= w || valid_prev) ? round_bf16(round_bf16(d) * 0.17677669529663687f) : -1e9f;
            }
            f = make_uint4(movmatrix_t(vf0.x), movmatrix_t(vf0.y), movmatrix_t(vf1.x), movmatrix_t(vf1.y));
            l = make_uint4(movmatrix_t(vl0.x), movmatrix_t(vl0.y), movmatrix_t(vl1.x), movmatrix_t(vl1.y));
            float m = lg[0];
#pragma unroll
            for (int w = 1; w < 8; w++) m = fmaxf(m, lg[w]);
            float sum = 0.f;
#pragma unroll
            for (int w = 0; w < 8; w++) {
              lg[w] = ex2_fast((lg[w] - m) * 1.4426950408889634f);
              sum += lg[w];
            }
            const float inv = gate * rcp_fast(sum);
            float o[8] = {0.f, 0.f, 0.f, 0.f, 0.f, 0.f, 0.f, 0.f};
#pragma unroll
            for (int w = 0; w < 8; w++) {
              const bool cur = g + w <= 7;
              const int src = (((g - w) & 7) << 2) | q;
              const uint32_t v0 = __shfl_sync(0xffffffffu, cur ? f.x : l.x, src), v1 = __shfl_sync(0xffffffffu, cur ? f.y : l.y, src);
              const uint32_t v2 = __shfl_sync(0xffffffffu, cur ? f.z : l.z, src), v3 = __shfl_sync(0xffffffffu, cur ? f.w : l.w, src);
              const float pw = round_bf16(lg[w] * inv);
              o[0] += pw * bf_lo(v0); o[1] += pw * bf_hi(v0);
              o[2] += pw * bf_lo(v1); o[3] += pw * bf_hi(v1);
              o[4] += pw * bf_lo(v2); o[5] += pw * bf_hi(v2);
              o[6] += pw * bf_lo(v3); o[7] += pw * bf_hi(v3);
            }
            const int r8 = lane & 7;
            stmatrix_x4(stg + r8 * 128 + (((4 * h + (lane >> 3)) ^ r8) << 4), pack_bf16(o[0], o[1]), pack_bf16(o[2], o[3]),
                        pack_bf16(o[4], o[5]), pack_bf16(o[6], o[7]));
          }
        }
        fence_async_smem();
        __syncwarp();
        if (lane == 0) {
          mbar_wait(sb + B_STG + 8 * cw, 0);
#pragma unroll 1
          for (int i = 0; i < 4; i++) {
            tma_st2(&p.zo, stg + i * 4096, cw * ZW + hp * 64, pb * 128 + i * 32);
            bulk_commit();
            bulk_wait_read0();
          }
          bulk_wait0();
          mbar_arrive(sb + B_FREE + 8 * cw);
          red_release_add(&g_sync[(SY_O + pb * 2 + (hp >> 3)) * 8], 1);
          const int c0 = 1024 + (int)rank * 1024 + jb * 256 + cw * 128;
#pragma unroll 1
          for (int w = 0; w < 2; w++) {
            mbar_wait(sb + B_STG + 16 + 16 * cw + 8 * w, 0);
            tma_st2(&p.zs, sb + SPARE + w * 16384, c0, rb * 128 + w * 64);
            bulk_commit();
            bulk_wait_read0();
            tma_st2(&p.zs, sb + SPARE + w * 16384 + 8192, c0 + 64, rb * 128 + w * 64);
            bulk_commit();
            bulk_wait_read0();
            if (cw == 0) mbar_arrive(sb + B_FREE + 16 + 8 * w);
          }
          bulk_wait0();
          red_release_add(&g_sync[(SY_PQ + rb * 4 + rank * 2 + cw) * 8], 1);
          const uint32_t rbar = mapa(sb + B_RECV + 8 * cw, rank ^ 1), rdst = mapa(stg, rank ^ 1);
          mbar_wait(sb + B_STG + 48 + 8 * cw, 0);
          bulk_copy_cl(rdst, sb + ((IT_B + 2) & 3) * ST2 + ST2_A + cw * 8192, 8192, rbar);
          mbar_wait(sb + B_X2 + 8 * cw, 0);
          bulk_copy_cl(rdst + 8192, sb + ((IT_B + 3) & 3) * ST2 + ST2_A + cw * 8192, 8192, rbar);
        }
        __syncwarp();
      }
    }
  } else {
    asm volatile("setmaxnreg.inc.sync.aligned.u32 %0;" ::"n"(224));
    const int cw = (warp >> 2) - 1, w4 = warp & 3, t128 = tid & 127;
    const int g = lane >> 2, q = lane & 3;
    const uint32_t stg = sb + SPARE + cw * 16384;
#define WAIT_FULL(it) do { mbar_wait(sb + B_FULL + 8 * ((it) & 3), ((it) >> 2) & 1); } while (0)
    const uint32_t rel_bar = mapa(sb + B_EMPTY, t128 & 1);
#define SCHED_FENCE() mbar_wait(sb + B_G, 0)
#define RELEASE(it) do { if (t128 < 2) mbar_arrive_cl(rel_bar + 8 * ((it) & 3)); } while (0)
    asm volatile("barrier.cluster.wait.aligned;" ::: "memory");
    const uint32_t sb16 = (sb & 0x3FFFF) >> 4, aoff16 = (ST2_A + cw * 8192) >> 4;
    float lg[8][2];
    uint32_t Vlo[16], Vhi[16];
    const bool c0cur = (2 * q <= g), c1cur = (2 * q + 1 <= g);
    {
      float qk[2][64], vt[64];
      const uint32_t a1off = (ST1_A + cw * 16384) >> 4;
      auto mma_qk = [&](uint32_t b16, int mb, int k, int accumulate) {
        wgmma_n128t<0, 1>(qk[mb], desc_k(b16 + a1off + mb * 512, k), desc_mn(b16, k), accumulate);
      };
      auto mma_vt = [&](uint32_t b16, int k, int accumulate) {
        wgmma_n128t<1, 0>(vt, desc_mn(b16 + 1024, k), desc_k(b16 + a1off, k), accumulate);
      };
      {
        mbar_wait(sb + B_F1, 0);
        mbar_wait(sb + B_F0 + 8 * cw, 0);
        wgmma_fence();
        mma_qk(sb16, 0, 0, 0);
        mma_qk(sb16, 0, 1, 1);
        WAIT_FULL(0);
        wgmma_fence();
        mma_qk(sb16, 0, 2, 1);
        mma_qk(sb16, 0, 3, 1);
        mbar_wait(sb + B_F0 + 16 + 8 * cw, 0);
        wgmma_fence();
#pragma unroll
        for (int k = 0; k < 4; k++) {
          mma_qk(sb16, 1, k, k != 0);
          mma_vt(sb16, k, k != 0);
        }
        wgmma_commit();
      }
#pragma unroll 1
      for (int it = 1; it < 15; it++) {
        const uint32_t b16 = sb16 + (it & 3) * (ST1 >> 4);
        WAIT_FULL(it);
        wgmma_fence();
#pragma unroll
        for (int k = 0; k < 4; k++) {
          mma_qk(b16, 0, k, 1);
          mma_qk(b16, 1, k, 1);
          mma_vt(b16, k, 1);
          if (k == 0) {
            wgmma_commit();
            wgmma_wait<1>();
            RELEASE(it - 1);
          }
        }
        wgmma_commit();
      }
      {
        const uint32_t b16 = sb16 + 3 * (ST1 >> 4);
        WAIT_FULL(15);
        wgmma_fence();
        mma_qk(b16, 0, 0, 1);
        mma_qk(b16, 1, 0, 1);
        wgmma_commit();
        wgmma_wait<1>();
        RELEASE(14);
#pragma unroll
        for (int k = 1; k < 4; k++) {
          mma_qk(b16, 0, k, 1);
          mma_qk(b16, 1, k, 1);
        }
        wgmma_commit();
#pragma unroll
        for (int k = 0; k < 4; k++) mma_vt(b16, k, 1);
        wgmma_commit();
      }
      mbar_wait(sb + B_G, 0);
      uint4* const edge = g_edge + ((pb * 16 + hp) * 2 + cw) * 12 * 32 + lane;
      const uint32_t hl = sb + 3 * ST2 + cw * 8192 + lane * 16;
      wgmma_wait<1>();
      fence_regs<0, 64>(qk[0]);
      fence_regs<0, 64>(qk[1]);
      uint32_t Qp[4][8], Kp[4][8], Kh[8];
#pragma unroll
      for (int j = 0; j < 8; j++) Kp[3][j] = pack_bf16(qk[1][4 * (8 + j) + 2], qk[1][4 * (8 + j) + 3]);
      sts128(hl + w4 * 1024, Kp[3][0], Kp[3][1], Kp[3][2], Kp[3][3]);
      sts128(hl + w4 * 1024 + 512, Kp[3][4], Kp[3][5], Kp[3][6], Kp[3][7]);
      named_bar_sync(1 + cw, 128);
      {
        const uint32_t hr = hl + ((w4 + 3) & 3) * 1024;
        uint4 v;
        v = lds128(hr); Kh[0] = v.x; Kh[1] = v.y; Kh[2] = v.z; Kh[3] = v.w;
        v = lds128(hr + 512); Kh[4] = v.x; Kh[5] = v.y; Kh[6] = v.z; Kh[7] = v.w;
      }
#pragma unroll
      for (int G = 0; G < 4; G++)
#pragma unroll
        for (int j = 0; j < 8; j++) {
          const int o = (G & 1) * 2;
          Qp[G][j] = pack_bf16(qk[G >> 1][4 * j + o], qk[G >> 1][4 * j + o + 1]);
          if (G < 3) Kp[G][j] = pack_bf16(qk[G >> 1][4 * (8 + j) + o], qk[G >> 1][4 * (8 + j) + o + 1]);
        }
      if (w4 == 0) {
#pragma unroll
        for (int c = 0; c < 4; c++) edge[c * 32] = make_uint4(Qp[0][2 * c], Qp[1][2 * c], Qp[0][2 * c + 1], Qp[1][2 * c + 1]);
        edge[4 * 32] = make_uint4(Kp[0][0], Kp[0][1], Kp[0][2], Kp[0][3]);
        edge[5 * 32] = make_uint4(Kp[0][4], Kp[0][5], Kp[0][6], Kp[0][7]);
      } else if (w4 == 3) {
        edge[6 * 32] = make_uint4(Kp[3][0], Kp[3][1], Kp[3][2], Kp[3][3]);
        edge[7 * 32] = make_uint4(Kp[3][4], Kp[3][5], Kp[3][6], Kp[3][7]);
      }
      wgmma_wait<0>();
      fence_regs<0, 64>(vt);
      float S[2][2][3][4];
#pragma unroll
      for (int ks = 0; ks < 2; ks++)
#pragma unroll
        for (int mb = 0; mb < 2; mb++)
#pragma unroll
          for (int h = 0; h < 2; h++)
#pragma unroll
            for (int kg = 0; kg < 3; kg++) {
              const int G0 = 2 * mb, G1 = 2 * mb + 1, j0 = 4 * h + 2 * ks;
              const bool halo = (G0 + kg == 0);
              const int Gk = halo ? 0 : G0 + kg - 1;
              float(&c)[4] = S[mb][h][kg];
              if (ks == 0) c[0] = c[1] = c[2] = c[3] = 0.f;
              mma_k16(c, Qp[G0][j0], Qp[G1][j0], Qp[G0][j0 + 1], Qp[G1][j0 + 1], halo ? Kh[j0] : Kp[Gk][j0],
                      halo ? Kh[j0 + 1] : Kp[Gk][j0 + 1]);
            }
#pragma unroll
      for (int R = 0; R < 16; R++) {
        const int cg = 8 * ((R >> 1) & 1) + 2 * (R >> 2) + (R & 1);
        Vlo[R] = pack_bf16(vt[4 * cg], vt[4 * cg + 1]);
        Vhi[R] = pack_bf16(vt[4 * cg + 2], vt[4 * cg + 3]);
      }
      edge[(8 + w4) * 32] = make_uint4(Vlo[0], Vhi[0], Vlo[15], Vhi[15]);
#pragma unroll
      for (int h = 0; h < 2; h++)
#pragma unroll
        for (int G = 0; G < 4; G++) {
          const int o = (G & 1) * 2, kg = G & 1;
          lg[4 * h + G][0] = c0cur ? S[G >> 1][h][kg + 1][o] : S[G >> 1][h][kg][o];
          lg[4 * h + G][1] = c1cur ? S[G >> 1][h][kg + 1][o + 1] : S[G >> 1][h][kg][o + 1];
        }
    }
    float acc[128];
    uint32_t pk[64], sp0, sp1;
    const uint32_t srow_off = (w4 * 16 + ((lane >> 3) & 1) * 8 + (lane & 7)) * 128;
    const uint32_t sx = (uint32_t)(lane & 7), shalf = (uint32_t)(lane >> 4);
    {
      {
        named_bar_sync(4, 256);
        RELEASE(15);
        if (lane == 0) mbar_arrive(sb + B_EDGE + 8 * cw);
        const uint32_t px = stg + 12288 + lane * 16;
        const uint32_t mcur = (c0cur ? 0xFFFFu : 0u) | (c1cur ? 0xFFFF0000u : 0u);
        uint32_t P[16];
        float O[16][4];
        auto kblock = [&](int it) {
          const uint32_t base = sb16 + (it & 3) * (ST2 >> 4);
          WAIT_FULL(it);
          wgmma_fence();
          mma256<1>(acc, base + aoff16, base, 0, it != 16);
          wgmma_commit();
          if (it != 16) {
            wgmma_wait<1>();
            RELEASE(it - 1);
          }
          mma256<1>(acc, base + aoff16, base, 1, 1);
          mma256<1>(acc, base + aoff16, base, 2, 1);
          mma256<1>(acc, base + aoff16, base, 3, 1);
          wgmma_commit();
          SCHED_FENCE();
        };
        auto stage_o = [&](int R0, int R1) {
          const uint32_t col = ((2 * w4 + ((lane >> 3) & 1)) ^ sx) << 4;
#pragma unroll
          for (int R = R0; R < R1; R += 2) {
            if (R == 0)
              stmatrix_x2_t(stg + (8 + sx) * 128 + col, pack_bf16v(O[1][0], O[1][1]), pack_bf16v(O[1][2], O[1][3]));
            else
              stmatrix_x4_t(stg + ((R + shalf) * 8 + sx) * 128 + col, pack_bf16v(O[R][0], O[R][1]),
                            pack_bf16v(O[R][2], O[R][3]), pack_bf16v(O[R + 1][0], O[R + 1][1]),
                            pack_bf16v(O[R + 1][2], O[R + 1][3]));
          }
        };
        float rr[8], gate[4];
        kblock(16);
#pragma unroll
        for (int i = 0; i < 8; i++) {
          uint32_t t = pack_bf16(lg[i][0], lg[i][1]);
          t = pack_bf16(bf_lo(t) * 0.17677669529663687f, bf_hi(t) * 0.17677669529663687f);
          lg[i][0] = bf_lo(t);
          lg[i][1] = bf_hi(t);
          float m = fmaxf(lg[i][0], lg[i][1]);
          m = fmaxf(m, __shfl_xor_sync(0xffffffffu, m, 1));
          rr[i] = fmaxf(m, __shfl_xor_sync(0xffffffffu, m, 2));
        }
        kblock(17);
#pragma unroll
        for (int G = 0; G < 4; G++) gate[G] = lds_f32(sb + S_G1 + (cw * 128 + w4 * 32 + G * 8 + g) * 4);
#pragma unroll
        for (int i = 0; i < 8; i++) {
          const float sc = 1.4426950408889634f;
          lg[i][0] = ex2_fast((lg[i][0] - rr[i]) * sc);
          lg[i][1] = ex2_fast((lg[i][1] - rr[i]) * sc);
          const float sum = lg[i][0] + lg[i][1];
          rr[i] = sum + __shfl_xor_sync(0xffffffffu, sum, 1);
        }
        kblock(18);
#pragma unroll
        for (int i = 0; i < 8; i++) {
          const float inv = gate[i & 3] * rcp_fast(rr[i] + __shfl_xor_sync(0xffffffffu, rr[i], 2));
          P[i] = pack_bf16(lg[i][0] * inv, lg[i][1] * inv);
        }
        sts128(px + w4 * 512, P[0], P[1], P[2], P[3]);
        sts128(px + 2048 + w4 * 512, P[4], P[5], P[6], P[7]);
        kblock(19);
        named_bar_sync(1 + cw, 128);
#pragma unroll
        for (int w = 0; w < 4; w++) {
          const uint4 v = lds128(px + (w4 >> 1) * 2048 + w * 512);
          P[4 * w] = v.x; P[4 * w + 1] = v.y; P[4 * w + 2] = v.z; P[4 * w + 3] = v.w;
        }
        uint32_t Pp[16];
#pragma unroll
        for (int R = 1; R < 16; R++) {
          Pp[R] = P[R] & ~mcur;
          P[R] &= mcur;
          asm volatile("" : "+r"(P[R]), "+r"(Pp[R]));
        }
        SCHED_FENCE();
        named_bar_sync(4, 256);
#pragma unroll
        for (int R = 1; R < 16; R++) {
          O[R][0] = O[R][1] = O[R][2] = O[R][3] = 0.f;
          mma_k16(O[R], Vlo[R - 1], Vhi[R - 1], Vlo[R], Vhi[R], Pp[R], P[R]);
        }
        kblock(20);
        stage_o(0, 8);
        kblock(21);
        stage_o(8, 16);
        kblock(22);
        fence_async_smem();
        __syncwarp();
        if (lane == 0) mbar_arrive(sb + B_STG + 8 * cw);
      }
#pragma unroll 1
      for (int it = 23; it < 48; it++) {
        const uint32_t base = sb16 + (it & 3) * (ST2 >> 4), sa = base + aoff16;
        const bool paused = (it == 47 && cw == 1);
        if (paused) {
          wgmma_wait<0>();
          RELEASE(46);
          named_bar_sync(3, 256);
        }
        WAIT_FULL(it);
        wgmma_fence();
        mma256<1>(acc, sa, base, 0, 1);
        wgmma_commit();
        wgmma_wait<1>();
        if (!paused) RELEASE(it - 1);
        mma256<1>(acc, sa, base, 1, 1);
        mma256<1>(acc, sa, base, 2, 1);
        mma256<1>(acc, sa, base, 3, 1);
        wgmma_commit();
      }
      if (cw == 0) named_bar_arrive(3, 256);
      const float s0 = lds_f32(sb + S_G2 + (cw * 64 + w4 * 16 + g) * 4), s1 = lds_f32(sb + S_G2 + (cw * 64 + w4 * 16 + g + 8) * 4);
      wgmma_wait<0>();
      fence_regs<0, 128>(acc);
      RELEASE(47);
#pragma unroll
      for (int j = 0; j < 32; j++) {
        pk[2 * j] = pack_bf16(acc[4 * j], acc[4 * j + 1]);
        pk[2 * j + 1] = pack_bf16(acc[4 * j + 2], acc[4 * j + 3]);
      }
      sp0 = pack_bf16(s0, s0);
      sp1 = pack_bf16(s1, s1);
    }
    {
      auto scale_half = [&](int half) {
#pragma unroll
        for (int i = 0; i < 32; i++) pk[32 * half + i] = mul_bf16x2v(pk[32 * half + i], (i & 1) ? sp1 : sp0);
      };
      auto stage_half = [&](int half) {
#pragma unroll
        for (int i = 0; i < 8; i++)
          stmatrix_x4(stg + (i >> 2) * 8192 + srow_off + ((((i & 3) * 2 + shalf) ^ sx) << 4), pk[32 * half + 4 * i],
                      pk[32 * half + 4 * i + 1], pk[32 * half + 4 * i + 2], pk[32 * half + 4 * i + 3]);
      };
      auto signal_half = [&](int half) {
        fence_async_smem();
        __syncwarp();
        if (lane == 0) mbar_arrive(sb + B_STG + 16 + 16 * half + 8 * cw);
      };
#pragma unroll
      for (int i = 0; i < 4; i++) {
        const int it = 48 + i;
        const uint32_t base = sb16 + i * (ST2 >> 4), sa = base + aoff16;
        if (i == 0) mbar_wait(sb + B_FREE + 8 * cw, 0);
        if (i == 3) mbar_wait(sb + B_FREE + 16 + 8 * cw, 0);
        WAIT_FULL(it);
        wgmma_fence();
        mma256<1>(acc, sa, base, 0, i != 0);
        wgmma_commit();
        if (i == 1) signal_half(0);
        if (i > 0) {
          wgmma_wait<1>();
          RELEASE(it - 1);
        }
        if (i == 1) wgmma_fence();
        mma256<1>(acc, sa, base, 1, 1);
        if (i == 0) scale_half(0);
        if (i == 2) scale_half(1);
        mma256<1>(acc, sa, base, 2, 1);
        if (i == 0) stage_half(0);
        if (i == 3) stage_half(1);
        mma256<1>(acc, sa, base, 3, 1);
        wgmma_commit();
      }
#pragma unroll
      for (int i = 0; i < 4; i++) {
        const int it = 52 + i, r0 = i * 16;
        const uint32_t base = sb16 + i * (ST2 >> 4);
        WAIT_FULL(it);
        wgmma_fence();
        wgmma_n256_rs(acc, pk[r0], pk[r0 + 1], pk[r0 + 2], pk[r0 + 3], desc_k(base, 0), 1);
        wgmma_commit();
        if (i == 0) signal_half(1);
        wgmma_wait<1>();
        RELEASE(it - 1);
        if (i == 0) wgmma_fence();
        wgmma_n256_rs(acc, pk[r0 + 4], pk[r0 + 5], pk[r0 + 6], pk[r0 + 7], desc_k(base, 1), 1);
        wgmma_n256_rs(acc, pk[r0 + 8], pk[r0 + 9], pk[r0 + 10], pk[r0 + 11], desc_k(base, 2), 1);
        wgmma_n256_rs(acc, pk[r0 + 12], pk[r0 + 13], pk[r0 + 14], pk[r0 + 15], desc_k(base, 3), 1);
        wgmma_commit();
      }
#pragma unroll 1
      for (int it = 56; it < 60; it++) {
        const uint32_t base = sb16 + (it & 3) * (ST2 >> 4), sa = base + aoff16;
        WAIT_FULL(it);
        wgmma_fence();
        mma256<1>(acc, sa, base, 0, 1);
        wgmma_commit();
        wgmma_wait<1>();
        RELEASE(it - 1);
        mma256<1>(acc, sa, base, 1, 1);
        mma256<1>(acc, sa, base, 2, 1);
        mma256<1>(acc, sa, base, 3, 1);
        wgmma_commit();
      }
#pragma unroll 1
      for (int it = 60; it < IT_B; it++) {
        const uint32_t base = sb16 + (it & 3) * (ST2 >> 4), sa = base + aoff16;
        const bool paused = (it == IT_B - 1 && cw == 1);
        if (paused) {
          wgmma_wait<0>();
          RELEASE(IT_B - 2);
          named_bar_sync(5, 256);
        }
        WAIT_FULL(it);
        wgmma_fence();
        mma256<0>(acc, sa, base, 0, 1);
        wgmma_commit();
        wgmma_wait<1>();
        if (!paused) RELEASE(it - 1);
        mma256<0>(acc, sa, base, 1, 1);
        mma256<0>(acc, sa, base, 2, 1);
        mma256<0>(acc, sa, base, 3, 1);
        wgmma_commit();
      }
      if (cw == 0) named_bar_arrive(5, 256);
      auto piece16 = [&](int pc) { return sb16 + ((IT_B + pc / 3) & 3) * (ST2 >> 4) + (pc % 3) * 1024; };
      const uint32_t xs0 = sb + ((IT_B + 2) & 3) * ST2 + ST2_A + cw * 8192 + w4 * 2048 + lane * 16;
      const uint32_t xs1 = sb + ((IT_B + 3) & 3) * ST2 + ST2_A + cw * 8192 + w4 * 2048 + lane * 16;
      auto stage_part = [&]() {
#pragma unroll
        for (int i = 0; i < 8; i++) {
          sts128((i < 4 ? xs0 : xs1) + (i & 3) * 512, pack_bf16v(acc[64 + 8 * i], acc[65 + 8 * i]),
                 pack_bf16v(acc[66 + 8 * i], acc[67 + 8 * i]), pack_bf16v(acc[68 + 8 * i], acc[69 + 8 * i]),
                 pack_bf16v(acc[70 + 8 * i], acc[71 + 8 * i]));
          if ((i & 3) == 3) {
            fence_async_smem();
            __syncwarp();
            if (lane == 0) mbar_arrive((i == 7 ? sb + B_X2 : sb + B_STG + 48) + 8 * cw);
          }
        }
      };
      WAIT_FULL(IT_B);
      wgmma_wait<0>();
      fence_regs<0, 128>(acc);
      stage_part();
      if (cw == 1) named_bar_sync(3, 256);
#pragma unroll
      for (int i = 0; i < KB3; i++) {
        const uint32_t sa = piece16(2 * i) + cw * 512, base = piece16(2 * i + 1);
        if (i > 0 && (2 * i + 1) / 3 != (2 * i - 1) / 3) WAIT_FULL(IT_B + (2 * i + 1) / 3);
        wgmma_fence();
#pragma unroll
        for (int k = 0; k < 4; k++) wgmma_n128_half<0, 0>(acc, desc_k(sa, k), desc_k(base, k));
        wgmma_commit();
      }
      if (cw == 0) named_bar_arrive(3, 256);
      mbar_wait_cluster(sb + B_RECV + 8 * cw, 0);
      asm volatile("barrier.cluster.arrive.relaxed.aligned;" ::: "memory");
      uint4 rx[8];
#pragma unroll
      for (int i = 0; i < 8; i++) rx[i] = lds128(stg + (i >> 2) * 8192 + w4 * 2048 + (i & 3) * 512 + lane * 16);
      float rf[64];
#pragma unroll
      for (int i = 0; i < 8; i++) {
        rf[8 * i] = bf_lo(rx[i].x); rf[8 * i + 1] = bf_hi(rx[i].x); rf[8 * i + 2] = bf_lo(rx[i].y); rf[8 * i + 3] = bf_hi(rx[i].y);
        rf[8 * i + 4] = bf_lo(rx[i].z); rf[8 * i + 5] = bf_hi(rx[i].z); rf[8 * i + 6] = bf_lo(rx[i].w); rf[8 * i + 7] = bf_hi(rx[i].w);
      }
      fence_regs<0, 64>(rf);
      wgmma_wait<0>();
      fence_regs<0, 64>(acc);
      const uint32_t ob = sb + (IT_B & 3) * ST2 + cw * 8192;
      const int c0 = jb * 256 + (int)rank * 128, r0 = rb * 128 + cw * 64 + w4 * 16;
#pragma unroll
      for (int b = 0; b < 2; b++) {
#pragma unroll
        for (int ii = 0; ii < 4; ii++) {
          const int i = 4 * b + ii;
          stmatrix_x4(ob + b * 32768 + srow_off + (((ii * 2 + shalf) ^ sx) << 4),
                      pack_bf16(acc[8 * i] + rf[8 * i], acc[8 * i + 1] + rf[8 * i + 1]),
                      pack_bf16(acc[8 * i + 2] + rf[8 * i + 2], acc[8 * i + 3] + rf[8 * i + 3]),
                      pack_bf16(acc[8 * i + 4] + rf[8 * i + 4], acc[8 * i + 5] + rf[8 * i + 5]),
                      pack_bf16(acc[8 * i + 6] + rf[8 * i + 6], acc[8 * i + 7] + rf[8 * i + 7]));
        }
        fence_async_smem();
        __syncwarp();
        if (lane == 0) tma_st2(&p.out, ob + b * 32768 + w4 * 2048, c0 + b * 64, r0);
      }
      if (lane == 0) {
        bulk_commit();
        bulk_wait_read0();
      }
      __syncwarp();
      asm volatile("barrier.cluster.wait.aligned;" ::: "memory");
    }
  }
}

typedef CUresult (*EncodeFn)(CUtensorMap*, CUtensorMapDataType, cuuint32_t, void*, const cuuint64_t*, const cuuint64_t*,
                             const cuuint32_t*, const cuuint32_t*, CUtensorMapInterleave, CUtensorMapSwizzle,
                             CUtensorMapL2promotion, CUtensorMapFloatOOBfill);

static bool make_map(EncodeFn enc, CUtensorMap* m, const void* ptr, int rank, const cuuint64_t* dims,
                     const cuuint64_t* strides, const cuuint32_t* box) {
  cuuint32_t es[5] = {1, 1, 1, 1, 1};
  CUresult r = enc(m, CU_TENSOR_MAP_DATA_TYPE_BFLOAT16, rank, const_cast<void*>(ptr), dims, strides, box, es,
                   CU_TENSOR_MAP_INTERLEAVE_NONE, CU_TENSOR_MAP_SWIZZLE_128B, CU_TENSOR_MAP_L2_PROMOTION_L2_128B,
                   CU_TENSOR_MAP_FLOAT_OOB_FILL_NONE);
  if (r != CUDA_SUCCESS) fprintf(stderr, "cuTensorMapEncodeTiled failed: %d\n", (int)r);
  return r == CUDA_SUCCESS;
}
static bool make_map2(EncodeFn enc, CUtensorMap* m, const void* ptr, uint64_t cols, uint64_t rows, uint32_t brows) {
  cuuint64_t dims[2] = {cols, rows}, str[1] = {cols * 2};
  cuuint32_t box[2] = {64, brows};
  return make_map(enc, m, ptr, 2, dims, str, box);
}

extern "C" void kernel_launch(void* const* d_in, const int* in_sizes, int n_in, void* d_out, int out_size) {
  (void)in_sizes; (void)n_in; (void)out_size;
  static EncodeFn enc = nullptr;
  static void* zptr = nullptr;
  if (!enc) {
    void* fn = nullptr;
    cudaDriverEntryPointQueryResult qr;
    cudaGetDriverEntryPoint("cuTensorMapEncodeTiled", &fn, cudaEnableDefault, &qr);
    enc = (EncodeFn)fn;
    cudaGetSymbolAddress(&zptr, g_Z);
    cudaFuncSetAttribute(fused_kernel, cudaFuncAttributeMaxDynamicSharedMemorySize, SMEM_BYTES);
  }
  const void *x = d_in[0], *wqkv = d_in[1], *wo = d_in[2], *cr = d_in[4], *ci = d_in[5], *dr = d_in[6], *di = d_in[7];
  Params p;
  {
    cuuint64_t dims[5] = {1024, 16, 32, 2, 2}, str[4] = {4096, 131072, 65536, 2048};
    cuuint32_t box[5] = {64, 16, 4, 2, 1};
    make_map(enc, &p.xa, x, 5, dims, str, box);
    cuuint32_t box1[5] = {64, 16, 4, 1, 1};
    make_map(enc, &p.xa1, x, 5, dims, str, box1);
  }
  {
    cuuint64_t dims[3] = {1024, 1024, 3}, str[2] = {6144, 2048};
    cuuint32_t box[3] = {64, 64, 3};
    make_map(enc, &p.wqkv, wqkv, 3, dims, str, box);
    cuuint32_t box1[3] = {64, 32, 1};
    make_map(enc, &p.wq1, wqkv, 3, dims, str, box1);
  }
  make_map2(enc, &p.c0, cr, 2048, 2048, 128);
  make_map2(enc, &p.c1, ci, 2048, 2048, 128);
  {
    cuuint64_t dims[3] = {64, 2048, 16}, str[2] = {2048, 128};
    cuuint32_t box[3] = {64, 64, 2};
    make_map(enc, &p.xb, x, 3, dims, str, box);
  }
  make_map2(enc, &p.zl, zptr, ZW, SEQ, 128);
  make_map2(enc, &p.zs, zptr, ZW, SEQ, 64);
  make_map2(enc, &p.zo, zptr, 2 * ZW, SEQ / 2, 32);
  make_map2(enc, &p.d0, dr, 1024, 1024, 128);
  make_map2(enc, &p.d1, di, 1024, 1024, 128);
  {
    cuuint64_t dims[3] = {64, 1024, 16}, str[2] = {2048, 128};
    cuuint32_t box[3] = {64, 64, 2};
    make_map(enc, &p.wo, wo, 3, dims, str, box);
  }
  make_map2(enc, &p.out, d_out, 1024, 2048, 16);
  p.x = (const __nv_bfloat16*)x;
  p.gate_w = (const __nv_bfloat16*)d_in[8];
  fused_kernel<<<128, 384, SMEM_BYTES>>>(p);
}
```
